```python
import torch

def _softmax(x, axis=-1):
    return torch.softmax(x, dim=axis)

def _gelu(x):
    return torch.nn.functional.gelu(x, approximate='tanh')

def _silu(x):
    return torch.nn.functional.silu(x)

def _sigmoid(x):
    return torch.sigmoid(x)

def _layernorm(x, axis=-1, eps=1e-05):
    m = x.mean(dim=axis, keepdim=True)
    v = x.var(dim=axis, keepdim=True, unbiased=False)
    return (x - m) / torch.sqrt(v + eps)

def _scatter_add(tgt, idx, src, axis=0):
    return tgt.clone().index_add_(axis, idx, src)

def _segment_sum(src, seg, n):
    out = torch.zeros((n,) + src.shape[1:], dtype=src.dtype)
    return out.index_add_(0, seg, src)

def _pad(x, pw):
    flat = tuple((v for pair in reversed(pw) for v in pair))
    return torch.nn.functional.pad(x, flat)
kernel_name = 'adaLN_cond__ssm_conv_s4__geglu_ffn__prompt'

def setup_inputs():

    _w = lambda a: (lambda t: t.to(torch.bfloat16) if t.is_floating_point() else t)(torch.as_tensor(a))

    def _A_setup():
        B, L, D, N = (1, 2048, 512, 128)
        A_re = -(lambda _x: torch.exp(torch.as_tensor(_x)))((lambda *s: torch.randn(*s, dtype=torch.bfloat16) * 3.2)(D, N))
        A_im = torch.pi * (lambda *s: torch.randn(*s, dtype=torch.bfloat16) * 0.1)(D, N)
        B_re = (lambda *s: torch.randn(*s, dtype=torch.bfloat16) * 0.2)(D, N)
        B_im = (lambda *s: torch.randn(*s, dtype=torch.bfloat16) * 0.2)(D, N)
        C_re = (lambda *s: torch.randn(*s, dtype=torch.bfloat16) * 0.2)(D, N)
        C_im = (lambda *s: torch.randn(*s, dtype=torch.bfloat16) * 0.2)(D, N)
        log_dt = (lambda *s: torch.randn(*s, dtype=torch.bfloat16) * 0.1)(D) * 0.5 - 4.0
        Dskip = (lambda *s: torch.randn(*s, dtype=torch.bfloat16) * 0.1)(D)
        return {'u': _w((lambda *s: torch.randn(*s, dtype=torch.bfloat16) * 0.05)(B, L, D)), 'A_re': _w(A_re), 'A_im': _w(A_im), 'B_re': _w(B_re), 'B_im': _w(B_im), 'C_re': _w(C_re), 'C_im': _w(C_im), 'log_dt': _w(log_dt), 'Dskip': _w(Dskip)}
    _A_in = _A_setup()

    def _B_setup():
        B, S, D, F = (1, 2048, 512, 1792)
        return {'x': _w((lambda *s: torch.randn(*s, dtype=torch.bfloat16) * 0.05)(B, S, D)), 'w_gate': _w((lambda *s: torch.randn(*s, dtype=torch.bfloat16) * 0.05)(D, F)), 'w_up': _w((lambda *s: torch.randn(*s, dtype=torch.bfloat16) * 0.05)(D, F)), 'w_down': _w((lambda *s: torch.randn(*s, dtype=torch.bfloat16) * 0.05)(F, D))}
    _B_in = _B_setup()
    return {'A_u': _A_in['u'], 'A_A_re': _A_in['A_re'], 'A_A_im': _A_in['A_im'], 'A_B_re': _A_in['B_re'], 'A_B_im': _A_in['B_im'], 'A_C_re': _A_in['C_re'], 'A_C_im': _A_in['C_im'], 'A_log_dt': _A_in['log_dt'], 'A_Dskip': _A_in['Dskip'], 'B_x': _B_in['x'], 'B_w_gate': _B_in['w_gate'], 'B_w_up': _B_in['w_up'], 'B_w_down': _B_in['w_down'], 'c': _w((lambda *s: torch.randn(*s, dtype=torch.bfloat16) * 0.1)(1, 512) * 8.0), 'w_mod': _w((lambda *s: torch.randn(*s, dtype=torch.bfloat16) * 0.1)(512, 6 * 512) * 512 ** (-0.5) * 8.0)}

def reference(A_u, A_A_re, A_A_im, A_B_re, A_B_im, A_C_re, A_C_im, A_log_dt, A_Dskip, B_x, B_w_gate, B_w_up, B_w_down, c, w_mod):

    def _A_ref(u, A_re, A_im, B_re, B_im, C_re, C_im, log_dt, Dskip):
        Bsz, L, D = u.shape
        dt = torch.exp(log_dt)[:, None]
        A = A_re + 1j * A_im
        Bc = B_re + 1j * B_im
        Cc = C_re + 1j * C_im
        logdA = dt * A
        dB = dt * Bc
        l = (lambda x, dt: x.to(dt))(torch.arange(L), A_re.dtype)
        P = torch.exp(logdA[:, :, None] * l[None, None, :])
        K = torch.einsum('dn,dnl,dn->dl', Cc, P, dB).real
        L2 = 2 * L
        Kp = _pad(K, ((0, 0), (0, L)))
        up = (lambda x, *d: x.permute(*d))(u, 0, 2, 1)
        up = _pad(up, ((0, 0), (0, 0), (0, L)))
        Kf = (lambda x, axes=(-2, -1): torch.fft.rfft2(x.float(), dim=axes))(Kp[:, None, :], axes=(-2, -1))
        Uf = (lambda x, axes=(-2, -1): torch.fft.rfft2(x.float(), dim=axes))(up[:, :, None, :], axes=(-2, -1))
        Yf = Uf * Kf[None, :, :, :]
        y = (lambda x, s, axes=(-2, -1): torch.fft.irfft2(x, s=s, dim=axes).to(torch.bfloat16))(Yf, (1, L2), axes=(-2, -1))[:, :, 0, :L]
        y = (lambda x, *d: x.permute(*d))(y, 0, 2, 1) + u * Dskip[None, None, :]
        return y

    def _B_ref(x, w_gate, w_up, w_down):
        return _gelu(x @ w_gate) * (x @ w_up) @ w_down
    x = A_u
    mod = (_silu(c) @ w_mod).reshape(c.shape[0], 6, 1, -1)
    sa, ca, ga, sb, cb, gb = (mod[:, 0].clone(), mod[:, 1].clone(), mod[:, 2].clone(), mod[:, 3].clone(), mod[:, 4].clone(), mod[:, 5].clone())
    h = _layernorm(x, axis=-1) * (1 + ca) + sa
    x = x + ga * _A_ref(h, A_A_re, A_A_im, A_B_re, A_B_im, A_C_re, A_C_im, A_log_dt, A_Dskip)
    h = _layernorm(x, axis=-1) * (1 + cb) + sb
    x = x + gb * _B_ref(h, B_w_gate, B_w_up, B_w_down)
    return x
```

```cpp
#include <cuda_runtime.h>
#include <cuda_bf16.h>
#include <cuda.h>
#include <stdint.h>

typedef __nv_bfloat16 bf16;
#define SPIN_MAX (1 << 17)
#define SKEW 0
#define YDEL 500
#define PDEL 1000
#define QDEL 350
#define HINT 1

struct Scr {
  uint4 XM[128 * 1024];
  uint4 YM[128 * 128 * 8];
  uint4 PM[128 * 2 * 4 * 256];
  uint4 H2[2048 * 64];
  uint4 X1[64];
  uint4 MODX[768];
  uint32_t epoch[128];
};
__device__ Scr g_s;
#define TSTAMP(i) do { } while (0)

struct Params {
  const bf16 *x, *Are, *Aim, *Bre, *Bim, *Cre, *Cim, *logdt, *dskip, *c;
  Scr* s;
  bf16* out;
  const bf16 *wg, *wu, *wd;
};

constexpr int SM_A = 0, SM_RING = 131072, SM_BAR = 229376, SM_RED = SM_BAR + 256, SM_REDM = SM_RED + 512, SM_SV = SM_REDM + 512, SM_TOTAL = SM_SV + 1024;
constexpr int STG_PITCH = 144, STG_WARP = 57 * 144;
constexpr int SM_MODS = 0, SM_STG = 24576, SM_HCH = SM_STG + 8 * STG_WARP, HCH_SZ = 8 * 656, SM_WIN = SM_HCH + 4 * HCH_SZ, WIN_SZ = 10240;
constexpr int SM_KAB = SM_WIN + 4 * WIN_SZ, KAB_SZ = 2 * 2592, SM_PQ = SM_KAB + 4 * KAB_SZ, PQ_SZ = 5184 + 1536;
constexpr int SM_FT = SM_PQ + 4 * PQ_SZ;
constexpr int FAR_OFF = 0, NEAR_OFF = 6912;
static_assert(SM_FT + 4096 <= SM_BAR && SM_FT % 16 == 0, "smem");
static_assert(NEAR_OFF + 32 * 272 <= 2 * STG_WARP, "smem");
static_assert(SM_TOTAL <= 232448, "smem");

__device__ __forceinline__ long long gtime() { long long t; asm volatile("mov.u64 %0, %globaltimer;" : "=l"(t)); return t; }
__device__ __forceinline__ uint32_t smem_u32(const void* p) { return (uint32_t)__cvta_generic_to_shared(p); }
__device__ __forceinline__ uint4 ld_b128(const uint4* p) {
  uint64_t a, b;
  asm volatile("{\n.reg .b128 t;\nld.relaxed.gpu.global.b128 t, [%2];\nmov.b128 {%0, %1}, t;\n}" : "=l"(a), "=l"(b) : "l"(p) : "memory");
  return make_uint4((uint32_t)a, (uint32_t)(a >> 32), (uint32_t)b, (uint32_t)(b >> 32));
}
__device__ __forceinline__ void st_b128(uint4* p, uint32_t x, uint32_t y, uint32_t z, uint32_t w) {
  uint64_t a = (uint64_t)x | ((uint64_t)y << 32), b = (uint64_t)z | ((uint64_t)w << 32);
  asm volatile("{\n.reg .b128 t;\nmov.b128 t, {%1, %2};\nst.relaxed.gpu.global.b128 [%0], t;\n}" ::"l"(p), "l"(a), "l"(b) : "memory");
}
__device__ __forceinline__ uint32_t ld_rlx(const uint32_t* p) { uint32_t v; asm volatile("ld.relaxed.gpu.global.u32 %0, [%1];" : "=r"(v) : "l"(p) : "memory"); return v; }
__device__ __forceinline__ void st_rlx(uint32_t* p, uint32_t v) { asm volatile("st.relaxed.gpu.global.u32 [%0], %1;" ::"l"(p), "r"(v) : "memory"); }
__device__ __forceinline__ uint2 ldg64(const void* p) { uint2 v; asm volatile("ld.global.nc.v2.u32 {%0, %1}, [%2];" : "=r"(v.x), "=r"(v.y) : "l"(p)); return v; }
__device__ __forceinline__ uint32_t ldg32(const void* p) { uint32_t v; asm volatile("ld.global.nc.u32 %0, [%1];" : "=r"(v) : "l"(p)); return v; }
__device__ __forceinline__ float ldg_bf(const bf16* p) { unsigned short v; asm volatile("ld.global.nc.u16 %0, [%1];" : "=h"(v) : "l"(p)); return __uint_as_float((uint32_t)v << 16); }
__device__ __forceinline__ float blo(uint32_t w) { return __uint_as_float(w << 16); }
__device__ __forceinline__ float bhi(uint32_t w) { return __uint_as_float(w & 0xffff0000u); }
__device__ __forceinline__ uint32_t pack2(float lo, float hi) { uint32_t d; asm("cvt.rn.bf16x2.f32 %0, %1, %2;" : "=r"(d) : "f"(hi), "f"(lo)); return d; }
__device__ __forceinline__ float rbf(float v) { return blo(pack2(v, 0.f)); }
__device__ __forceinline__ uint32_t hadd2(uint32_t a, uint32_t b) { uint32_t d; asm("add.rn.bf16x2 %0, %1, %2;" : "=r"(d) : "r"(a), "r"(b)); return d; }
__device__ __forceinline__ uint32_t hsub2(uint32_t a, uint32_t b) { uint32_t d; asm("sub.rn.bf16x2 %0, %1, %2;" : "=r"(d) : "r"(a), "r"(b)); return d; }
__device__ __forceinline__ uint32_t hmul2(uint32_t a, uint32_t b) { uint32_t d; asm("mul.rn.bf16x2 %0, %1, %2;" : "=r"(d) : "r"(a), "r"(b)); return d; }
__device__ __forceinline__ uint32_t dup_lo(uint32_t w) { return __byte_perm(w, w, 0x1010); }
__device__ __forceinline__ uint32_t dup_hi(uint32_t w) { return __byte_perm(w, w, 0x3232); }
__device__ __forceinline__ void bar_sync(int id, int n) { asm volatile("bar.sync %0, %1;" ::"r"(id), "r"(n) : "memory"); }
__device__ __forceinline__ void bar_arrive(int id, int n) { asm volatile("bar.arrive %0, %1;" ::"r"(id), "r"(n) : "memory"); }
__device__ __forceinline__ void sts32(uint32_t a, uint32_t v) { asm volatile("st.shared.u32 [%0], %1;" ::"r"(a), "r"(v) : "memory"); }
__device__ __forceinline__ void sts32f(uint32_t a, float v) { asm volatile("st.shared.f32 [%0], %1;" ::"r"(a), "f"(v) : "memory"); }
__device__ __forceinline__ void sts64(uint32_t a, uint32_t x, uint32_t y) { asm volatile("st.shared.v2.u32 [%0], {%1, %2};" ::"r"(a), "r"(x), "r"(y) : "memory"); }
__device__ __forceinline__ void sts64f(uint32_t a, float x, float y) { asm volatile("st.shared.v2.f32 [%0], {%1, %2};" ::"r"(a), "f"(x), "f"(y) : "memory"); }
__device__ __forceinline__ void sts128(uint32_t a, uint32_t x, uint32_t y, uint32_t z, uint32_t w) { asm volatile("st.shared.v4.u32 [%0], {%1, %2, %3, %4};" ::"r"(a), "r"(x), "r"(y), "r"(z), "r"(w) : "memory"); }
__device__ __forceinline__ uint32_t lds32(uint32_t a) { uint32_t v; asm volatile("ld.shared.u32 %0, [%1];" : "=r"(v) : "r"(a) : "memory"); return v; }
__device__ __forceinline__ float lds32f(uint32_t a) { float v; asm volatile("ld.shared.f32 %0, [%1];" : "=f"(v) : "r"(a) : "memory"); return v; }
__device__ __forceinline__ float2 lds64f(uint32_t a) { float2 v; asm volatile("ld.shared.v2.f32 {%0, %1}, [%2];" : "=f"(v.x), "=f"(v.y) : "r"(a) : "memory"); return v; }
__device__ __forceinline__ uint2 lds64(uint32_t a) { uint2 v; asm volatile("ld.shared.v2.u32 {%0, %1}, [%2];" : "=r"(v.x), "=r"(v.y) : "r"(a) : "memory"); return v; }
__device__ __forceinline__ uint4 lds128(uint32_t a) { uint4 v; asm volatile("ld.shared.v4.u32 {%0, %1, %2, %3}, [%4];" : "=r"(v.x), "=r"(v.y), "=r"(v.z), "=r"(v.w) : "r"(a) : "memory"); return v; }
__device__ __forceinline__ void ldsm4(uint32_t (&r)[4], uint32_t a) { asm volatile("ldmatrix.sync.aligned.m8n8.x4.shared.b16 {%0, %1, %2, %3}, [%4];" : "=r"(r[0]), "=r"(r[1]), "=r"(r[2]), "=r"(r[3]) : "r"(a) : "memory"); }
__device__ __forceinline__ void ldsm4t(uint32_t (&r)[4], uint32_t a) { asm volatile("ldmatrix.sync.aligned.m8n8.x4.trans.shared.b16 {%0, %1, %2, %3}, [%4];" : "=r"(r[0]), "=r"(r[1]), "=r"(r[2]), "=r"(r[3]) : "r"(a) : "memory"); }
__device__ __forceinline__ void ldsm1(uint32_t& r, uint32_t a) { asm volatile("ldmatrix.sync.aligned.m8n8.x1.shared.b16 {%0}, [%1];" : "=r"(r) : "r"(a) : "memory"); }
__device__ __forceinline__ void stsm4(uint32_t a, uint32_t x, uint32_t y, uint32_t z, uint32_t w) { asm volatile("stmatrix.sync.aligned.m8n8.x4.shared.b16 [%0], {%1, %2, %3, %4};" ::"r"(a), "r"(x), "r"(y), "r"(z), "r"(w) : "memory"); }
__device__ __forceinline__ void stsm4t(uint32_t a, uint32_t x, uint32_t y, uint32_t z, uint32_t w) { asm volatile("stmatrix.sync.aligned.m8n8.x4.trans.shared.b16 [%0], {%1, %2, %3, %4};" ::"r"(a), "r"(x), "r"(y), "r"(z), "r"(w) : "memory"); }
__device__ __forceinline__ void mma16816(float (&d)[4], uint32_t a0, uint32_t a1, uint32_t a2, uint32_t a3, uint32_t b0, uint32_t b1) {
  asm volatile("mma.sync.aligned.m16n8k16.row.col.f32.bf16.bf16.f32 {%0, %1, %2, %3}, {%4, %5, %6, %7}, {%8, %9}, {%0, %1, %2, %3};"
               : "+f"(d[0]), "+f"(d[1]), "+f"(d[2]), "+f"(d[3]) : "r"(a0), "r"(a1), "r"(a2), "r"(a3), "r"(b0), "r"(b1));
}
__device__ __forceinline__ void mbar_init(uint32_t b, int n) { asm volatile("mbarrier.init.shared::cta.b64 [%0], %1;" ::"r"(b), "r"(n) : "memory"); }
__device__ __forceinline__ void mbar_expect(uint32_t b, int bytes) { asm volatile("mbarrier.arrive.expect_tx.shared::cta.b64 _, [%0], %1;" ::"r"(b), "r"(bytes) : "memory"); }
__device__ __forceinline__ void mbar_wait(uint32_t b, int parity) {
  uint32_t ok;
  int it = 0;
  do {
    asm volatile("{\n.reg .pred p;\nmbarrier.try_wait.parity.shared::cta.b64 p, [%1], %2;\nselp.u32 %0, 1, 0, p;\n}" : "=r"(ok) : "r"(b), "r"(parity) : "memory");
  } while (!ok && ++it < SPIN_MAX);
}
__device__ __forceinline__ void mbar_arrive_cl(uint32_t cb) { asm volatile("mbarrier.arrive.shared::cluster.b64 _, [%0];" ::"r"(cb) : "memory"); }
__device__ __forceinline__ void mbar_arrive(uint32_t cb) { asm volatile("mbarrier.arrive.shared::cta.b64 _, [%0];" ::"r"(cb) : "memory"); }
__device__ __forceinline__ uint32_t mapa(uint32_t a, uint32_t r) { uint32_t d; asm("mapa.shared::cluster.u32 %0, %1, %2;" : "=r"(d) : "r"(a), "r"(r)); return d; }
__device__ __forceinline__ void tma2d(uint32_t dst, const CUtensorMap* tm, uint32_t bar, int c0, int c1) {
  asm volatile("cp.async.bulk.tensor.2d.shared::cluster.global.mbarrier::complete_tx::bytes [%0], [%1, {%3, %4}], [%2];" ::"r"(dst), "l"(tm), "r"(bar), "r"(c0), "r"(c1) : "memory");
}
__device__ __forceinline__ void tma3d(uint32_t dst, const CUtensorMap* tm, uint32_t bar, int c0, int c1, int c2) {
  asm volatile("cp.async.bulk.tensor.3d.shared::cluster.global.mbarrier::complete_tx::bytes [%0], [%1, {%3, %4, %5}], [%2];" ::"r"(dst), "l"(tm), "r"(bar), "r"(c0), "r"(c1), "r"(c2) : "memory");
}
__device__ __forceinline__ void st_async(uint32_t a, uint32_t x, uint32_t y, uint32_t z, uint32_t w, uint32_t bar) {
  asm volatile("st.async.weak.shared::cluster.mbarrier::complete_tx::bytes.v4.b32 [%0], {%1, %2, %3, %4}, [%5];" ::"r"(a), "r"(x), "r"(y), "r"(z), "r"(w), "r"(bar) : "memory");
}
__device__ __forceinline__ void wg_fence() { asm volatile("wgmma.fence.sync.aligned;" ::: "memory"); }
__device__ __forceinline__ void wg_commit() { asm volatile("wgmma.commit_group.sync.aligned;" ::: "memory"); }
template <int N> __device__ __forceinline__ void wg_wait() { asm volatile("wgmma.wait_group.sync.aligned %0;" ::"n"(N) : "memory"); }
template <int N> __device__ __forceinline__ void reg_fence(float (&d)[N]) {
#pragma unroll
  for (int i = 0; i < N; i++) asm volatile("" : "+f"(d[i])::"memory");
}
__device__ __forceinline__ uint64_t mkdesc(uint32_t addr, uint32_t lbo, uint32_t sbo, uint32_t mode) {
  return (uint64_t)((addr & 0x3FFFF) >> 4) | ((uint64_t)(lbo >> 4) << 16) | ((uint64_t)(sbo >> 4) << 32) | ((uint64_t)mode << 62);
}
__device__ __forceinline__ float tanh_ap(float x) { float y; asm("tanh.approx.f32 %0, %1;" : "=f"(y) : "f"(x)); return y; }
__device__ __forceinline__ float ex2_ap(float x) { float y; asm("ex2.approx.f32 %0, %1;" : "=f"(y) : "f"(x)); return y; }
struct cpx { float r, i; };
__device__ __forceinline__ cpx cmul(cpx a, cpx b) { cpx d; d.r = fmaf(a.r, b.r, -a.i * b.i); d.i = fmaf(a.r, b.i, a.i * b.r); return d; }
__device__ __forceinline__ cpx cexpk(float l2, float tt, float k) {
  float mag = ex2_ap(l2 * k);
  float ph = tt * k;
  ph = (ph - rintf(ph)) * 6.283185307179586f;
  cpx d; d.r = mag * __cosf(ph); d.i = mag * __sinf(ph);
  return d;
}
__device__ __forceinline__ cpx csq(cpx a) { cpx d; d.r = fmaf(a.r, a.r, -a.i * a.i); d.i = (a.r + a.r) * a.i; return d; }
__device__ __forceinline__ cpx cmulc(cpx a, cpx b) { cpx d; d.r = fmaf(a.r, b.r, a.i * b.i); d.i = fmaf(a.i, b.r, -a.r * b.i); return d; }
__device__ __forceinline__ float geglu2(float g, float u) {
  float t = tanh_ap(g * fmaf(g * g, 0.0356774081363001f, 0.7978845608028654f));
  float hg = g * u;
  return fmaf(hg, t, hg);
}
__device__ __forceinline__ uint32_t hfma2(uint32_t a, uint32_t b, uint32_t c) { uint32_t d; asm("fma.rn.bf16x2 %0, %1, %2, %3;" : "=r"(d) : "r"(a), "r"(b), "r"(c)); return d; }
__device__ __forceinline__ uint4 ldg128(const void* p) { uint4 v; asm volatile("ld.global.nc.v4.u32 {%0, %1, %2, %3}, [%4];" : "=r"(v.x), "=r"(v.y), "=r"(v.z), "=r"(v.w) : "l"(p)); return v; }
__device__ __forceinline__ float rcp_ap(float x) { float y; asm("rcp.approx.ftz.f32 %0, %1;" : "=f"(y) : "f"(x)); return y; }
__device__ __forceinline__ float sqrt_ap(float x) { float y; asm("sqrt.approx.f32 %0, %1;" : "=f"(y) : "f"(x)); return y; }
#define PLO(a, b) __byte_perm(a, b, 0x5410)
#define PHI(a, b) __byte_perm(a, b, 0x7632)
__device__ __forceinline__ void wgmma_rs32(float (&d)[16], uint32_t a0, uint32_t a1, uint32_t a2, uint32_t a3, uint64_t db, int sd) {
  asm volatile("{\n.reg .pred p;\nsetp.ne.b32 p, %21, 0;\n"
    "wgmma.mma_async.sync.aligned.m64n32k16.f32.bf16.bf16 {%0,%1,%2,%3,%4,%5,%6,%7,%8,%9,%10,%11,%12,%13,%14,%15}, {%16,%17,%18,%19}, %20, p, 1, 1, 0;\n}"
    : "+f"(d[0]), "+f"(d[1]), "+f"(d[2]), "+f"(d[3]), "+f"(d[4]), "+f"(d[5]), "+f"(d[6]), "+f"(d[7]), "+f"(d[8]), "+f"(d[9]), "+f"(d[10]), "+f"(d[11]), "+f"(d[12]), "+f"(d[13]), "+f"(d[14]), "+f"(d[15])
    : "r"(a0), "r"(a1), "r"(a2), "r"(a3), "l"(db), "r"(sd));
}
#define FENCE_ASYNC() asm volatile("fence.proxy.async.shared::cta;" ::: "memory")
__device__ __forceinline__ void wgmma_ss256(float (&d)[128], uint64_t da, uint64_t db, int sd) {
  asm volatile("{\n.reg .pred p;\nsetp.ne.b32 p, %130, 0;\n"
    "wgmma.mma_async.sync.aligned.m64n256k16.f32.bf16.bf16 {%0, %1, %2, %3, %4, %5, %6, %7, %8, %9, %10, %11, %12, %13, %14, %15, %16, %17, %18, %19, %20, %21, %22, %23, %24, %25, %26, %27, %28, %29, %30, %31, %32, %33, %34, %35, %36, %37, %38, %39, %40, %41, %42, %43, %44, %45, %46, %47, %48, %49, %50, %51, %52, %53, %54, %55, %56, %57, %58, %59, %60, %61, %62, %63, %64, %65, %66, %67, %68, %69, %70, %71, %72, %73, %74, %75, %76, %77, %78, %79, %80, %81, %82, %83, %84, %85, %86, %87, %88, %89, %90, %91, %92, %93, %94, %95, %96, %97, %98, %99, %100, %101, %102, %103, %104, %105, %106, %107, %108, %109, %110, %111, %112, %113, %114, %115, %116, %117, %118, %119, %120, %121, %122, %123, %124, %125, %126, %127}, %128, %129, p, 1, 1, 0, 1;\n}\n"
    : "+f"(d[0]), "+f"(d[1]), "+f"(d[2]), "+f"(d[3]), "+f"(d[4]), "+f"(d[5]), "+f"(d[6]), "+f"(d[7]), "+f"(d[8]), "+f"(d[9]), "+f"(d[10]), "+f"(d[11]), "+f"(d[12]), "+f"(d[13]), "+f"(d[14]), "+f"(d[15]), "+f"(d[16]), "+f"(d[17]), "+f"(d[18]), "+f"(d[19]), "+f"(d[20]), "+f"(d[21]), "+f"(d[22]), "+f"(d[23]), "+f"(d[24]), "+f"(d[25]), "+f"(d[26]), "+f"(d[27]), "+f"(d[28]), "+f"(d[29]), "+f"(d[30]), "+f"(d[31]), "+f"(d[32]), "+f"(d[33]), "+f"(d[34]), "+f"(d[35]), "+f"(d[36]), "+f"(d[37]), "+f"(d[38]), "+f"(d[39]), "+f"(d[40]), "+f"(d[41]), "+f"(d[42]), "+f"(d[43]), "+f"(d[44]), "+f"(d[45]), "+f"(d[46]), "+f"(d[47]), "+f"(d[48]), "+f"(d[49]), "+f"(d[50]), "+f"(d[51]), "+f"(d[52]), "+f"(d[53]), "+f"(d[54]), "+f"(d[55]), "+f"(d[56]), "+f"(d[57]), "+f"(d[58]), "+f"(d[59]), "+f"(d[60]), "+f"(d[61]), "+f"(d[62]), "+f"(d[63]), "+f"(d[64]), "+f"(d[65]), "+f"(d[66]), "+f"(d[67]), "+f"(d[68]), "+f"(d[69]), "+f"(d[70]), "+f"(d[71]), "+f"(d[72]), "+f"(d[73]), "+f"(d[74]), "+f"(d[75]), "+f"(d[76]), "+f"(d[77]), "+f"(d[78]), "+f"(d[79]), "+f"(d[80]), "+f"(d[81]), "+f"(d[82]), "+f"(d[83]), "+f"(d[84]), "+f"(d[85]), "+f"(d[86]), "+f"(d[87]), "+f"(d[88]), "+f"(d[89]), "+f"(d[90]), "+f"(d[91]), "+f"(d[92]), "+f"(d[93]), "+f"(d[94]), "+f"(d[95]), "+f"(d[96]), "+f"(d[97]), "+f"(d[98]), "+f"(d[99]), "+f"(d[100]), "+f"(d[101]), "+f"(d[102]), "+f"(d[103]), "+f"(d[104]), "+f"(d[105]), "+f"(d[106]), "+f"(d[107]), "+f"(d[108]), "+f"(d[109]), "+f"(d[110]), "+f"(d[111]), "+f"(d[112]), "+f"(d[113]), "+f"(d[114]), "+f"(d[115]), "+f"(d[116]), "+f"(d[117]), "+f"(d[118]), "+f"(d[119]), "+f"(d[120]), "+f"(d[121]), "+f"(d[122]), "+f"(d[123]), "+f"(d[124]), "+f"(d[125]), "+f"(d[126]), "+f"(d[127])
    : "l"(da), "l"(db), "r"(sd));
}
__device__ __forceinline__ void wgmma_ss128(float (&d)[64], uint64_t da, uint64_t db, int sd) {
  asm volatile("{\n.reg .pred p;\nsetp.ne.b32 p, %66, 0;\n"
    "wgmma.mma_async.sync.aligned.m64n128k16.f32.bf16.bf16 {%0, %1, %2, %3, %4, %5, %6, %7, %8, %9, %10, %11, %12, %13, %14, %15, %16, %17, %18, %19, %20, %21, %22, %23, %24, %25, %26, %27, %28, %29, %30, %31, %32, %33, %34, %35, %36, %37, %38, %39, %40, %41, %42, %43, %44, %45, %46, %47, %48, %49, %50, %51, %52, %53, %54, %55, %56, %57, %58, %59, %60, %61, %62, %63}, %64, %65, p, 1, 1, 0, 1;\n}\n"
    : "+f"(d[0]), "+f"(d[1]), "+f"(d[2]), "+f"(d[3]), "+f"(d[4]), "+f"(d[5]), "+f"(d[6]), "+f"(d[7]), "+f"(d[8]), "+f"(d[9]), "+f"(d[10]), "+f"(d[11]), "+f"(d[12]), "+f"(d[13]), "+f"(d[14]), "+f"(d[15]), "+f"(d[16]), "+f"(d[17]), "+f"(d[18]), "+f"(d[19]), "+f"(d[20]), "+f"(d[21]), "+f"(d[22]), "+f"(d[23]), "+f"(d[24]), "+f"(d[25]), "+f"(d[26]), "+f"(d[27]), "+f"(d[28]), "+f"(d[29]), "+f"(d[30]), "+f"(d[31]), "+f"(d[32]), "+f"(d[33]), "+f"(d[34]), "+f"(d[35]), "+f"(d[36]), "+f"(d[37]), "+f"(d[38]), "+f"(d[39]), "+f"(d[40]), "+f"(d[41]), "+f"(d[42]), "+f"(d[43]), "+f"(d[44]), "+f"(d[45]), "+f"(d[46]), "+f"(d[47]), "+f"(d[48]), "+f"(d[49]), "+f"(d[50]), "+f"(d[51]), "+f"(d[52]), "+f"(d[53]), "+f"(d[54]), "+f"(d[55]), "+f"(d[56]), "+f"(d[57]), "+f"(d[58]), "+f"(d[59]), "+f"(d[60]), "+f"(d[61]), "+f"(d[62]), "+f"(d[63])
    : "l"(da), "l"(db), "r"(sd));
}
__device__ __forceinline__ void wgmma_ss64(float (&d)[32], uint64_t da, uint64_t db, int sd) {
  asm volatile("{\n.reg .pred p;\nsetp.ne.b32 p, %34, 0;\n"
    "wgmma.mma_async.sync.aligned.m64n64k16.f32.bf16.bf16 {%0, %1, %2, %3, %4, %5, %6, %7, %8, %9, %10, %11, %12, %13, %14, %15, %16, %17, %18, %19, %20, %21, %22, %23, %24, %25, %26, %27, %28, %29, %30, %31}, %32, %33, p, 1, 1, 0, 1;\n}\n"
    : "+f"(d[0]), "+f"(d[1]), "+f"(d[2]), "+f"(d[3]), "+f"(d[4]), "+f"(d[5]), "+f"(d[6]), "+f"(d[7]), "+f"(d[8]), "+f"(d[9]), "+f"(d[10]), "+f"(d[11]), "+f"(d[12]), "+f"(d[13]), "+f"(d[14]), "+f"(d[15]), "+f"(d[16]), "+f"(d[17]), "+f"(d[18]), "+f"(d[19]), "+f"(d[20]), "+f"(d[21]), "+f"(d[22]), "+f"(d[23]), "+f"(d[24]), "+f"(d[25]), "+f"(d[26]), "+f"(d[27]), "+f"(d[28]), "+f"(d[29]), "+f"(d[30]), "+f"(d[31])
    : "l"(da), "l"(db), "r"(sd));
}
__device__ __forceinline__ void wgmma_rs64n(float (&d)[32], uint32_t a0, uint32_t a1, uint32_t a2, uint32_t a3, uint64_t db, int sd) {
  asm volatile("{\n.reg .pred p;\nsetp.ne.b32 p, %37, 0;\n"
    "wgmma.mma_async.sync.aligned.m64n64k16.f32.bf16.bf16 {%0, %1, %2, %3, %4, %5, %6, %7, %8, %9, %10, %11, %12, %13, %14, %15, %16, %17, %18, %19, %20, %21, %22, %23, %24, %25, %26, %27, %28, %29, %30, %31}, {%32, %33, %34, %35}, %36, p, 1, 1, 1;\n}\n"
    : "+f"(d[0]), "+f"(d[1]), "+f"(d[2]), "+f"(d[3]), "+f"(d[4]), "+f"(d[5]), "+f"(d[6]), "+f"(d[7]), "+f"(d[8]), "+f"(d[9]), "+f"(d[10]), "+f"(d[11]), "+f"(d[12]), "+f"(d[13]), "+f"(d[14]), "+f"(d[15]), "+f"(d[16]), "+f"(d[17]), "+f"(d[18]), "+f"(d[19]), "+f"(d[20]), "+f"(d[21]), "+f"(d[22]), "+f"(d[23]), "+f"(d[24]), "+f"(d[25]), "+f"(d[26]), "+f"(d[27]), "+f"(d[28]), "+f"(d[29]), "+f"(d[30]), "+f"(d[31])
    : "r"(a0), "r"(a1), "r"(a2), "r"(a3), "l"(db), "r"(sd));
}

__global__ void __cluster_dims__(2, 1, 1) __launch_bounds__(384, 1)
fused_kernel(const Params p, const __grid_constant__ CUtensorMap tmM, const __grid_constant__ CUtensorMap tmG1, const __grid_constant__ CUtensorMap tmU1,
             const __grid_constant__ CUtensorMap tmG2, const __grid_constant__ CUtensorMap tmU2, const __grid_constant__ CUtensorMap tmD,
             const __grid_constant__ CUtensorMap tmG3, const __grid_constant__ CUtensorMap tmU3,
             const __grid_constant__ CUtensorMap tmD2, const __grid_constant__ CUtensorMap tmD3) {
  extern __shared__ __align__(1024) uint8_t smem_raw[];
  const uint32_t sb = smem_u32(smem_raw);
  const int tid = threadIdx.x, warp = __shfl_sync(~0u, tid >> 5, 0), lane = tid & 31, b = blockIdx.x;
  const int rank = b & 1, f = b & 7, m = b >> 3, jb = b;
  const int g = lane >> 2, c4 = lane & 3, ch = warp & 3;
  const uint32_t barF = sb + SM_BAR, barE = barF + 48, barA = barF + 96, barR = barF + 128, barM = barF + 160, barQ = barF + 168, barP = barF + 176;
  uint32_t ep;
  const uint32_t hch = sb + SM_HCH + ch * HCH_SZ;
  const uint32_t stgc = sb + SM_STG + ch * 2 * STG_WARP;
  const uint32_t kab = sb + SM_KAB + ch * KAB_SZ;
  const uint32_t pq = sb + SM_PQ + ch * PQ_SZ;
  int ru0 = warp, rust = 8;
  if (tid == 0) TSTAMP(0);

  if (warp >= 8) {
    const int w = warp - 8, t2 = tid - 256;
    const int xoff = (16 * jb + 2 * g) * 512 + 128 * w + 8 * c4;
    uint32_t xa[16], xb[16];
#pragma unroll
    for (int i = 0; i < 4; i++) {
      uint4 u = ldg128(p.x + xoff + 32 * i), v = ldg128(p.x + xoff + 512 + 32 * i);
      xa[4 * i] = u.x; xa[4 * i + 1] = u.y; xa[4 * i + 2] = u.z; xa[4 * i + 3] = u.w;
      xb[4 * i] = v.x; xb[4 * i + 1] = v.y; xb[4 * i + 2] = v.z; xb[4 * i + 3] = v.w;
    }
    const uint2 cv = ldg64(p.c + 4 * t2);
    ep = ld_rlx(p.s->epoch + b) + 1;
    uint4 sa = ld_b128(p.s->MODX + b), ca = ld_b128(p.s->MODX + 128 + b);
    if (t2 == 0) {
      for (int i = 0; i < 25; i++) mbar_init(barF + 8 * i, ((i >= 6 && i < 12) || i > 20) ? 8 : 1);
      asm volatile("fence.mbarrier_init.release.cluster;" ::: "memory");
      mbar_expect(barM, 24576);
      if (b < 43) { tma2d(sb + SM_MODS, &tmM, barM, 24 * b, 0); tma2d(sb + SM_MODS + 12288, &tmM, barM, 24 * b, 256); }
    }
    for (int i = lane; i < 72; i += 32) sts128(hch + (i & 7) * 656 + (i >> 3) * 16, 0, 0, 0, 0);
    {
      float s0 = blo(cv.x), s1 = bhi(cv.x), s2 = blo(cv.y), s3 = bhi(cv.y);
      sts64(sb + SM_SV + t2 * 8, pack2(__fdividef(s0, 1.f + __expf(-s0)), __fdividef(s1, 1.f + __expf(-s1))),
            pack2(__fdividef(s2, 1.f + __expf(-s2)), __fdividef(s3, 1.f + __expf(-s3))));
    }
    uint32_t cbw[16], sbw[16];
    const uint32_t par = ep & 1;
#pragma unroll 1
    for (int phase = 0; phase < 2; phase++) {
      uint32_t na[16], nb[16];
      {
        float s[2][4], qa[2][4], qb[2][4];
#pragma unroll
        for (int i = 0; i < 8; i++) s[i >> 2][i & 3] = qa[i >> 2][i & 3] = qb[i >> 2][i & 3] = 0.f;
#pragma unroll
        for (int i = 0; i < 8; i++) {
          mma16816(s[i & 1], xa[2 * i], xb[2 * i], xa[2 * i + 1], xb[2 * i + 1], 0x3f803f80u, 0x3f803f80u);
          mma16816(qa[i & 1], xa[2 * i], xb[2 * i], xa[2 * i + 1], xb[2 * i + 1], xa[2 * i], xa[2 * i + 1]);
          mma16816(qb[i & 1], xa[2 * i], xb[2 * i], xa[2 * i + 1], xb[2 * i + 1], xb[2 * i], xb[2 * i + 1]);
        }
        if (t2 == 0 && phase == 0 && b >= 43 && s[0][0] != 1e30f) { tma2d(sb + SM_MODS, &tmM, barM, 24 * b, 0); tma2d(sb + SM_MODS + 12288, &tmM, barM, 24 * b, 256); }
        if (c4 == (g >> 1))
          sts128(sb + SM_RED + (w * 8 + g) * 16, __float_as_uint(s[0][0] + s[1][0]), __float_as_uint(s[0][2] + s[1][2]),
                 __float_as_uint((g & 1) ? qa[0][1] + qa[1][1] : qa[0][0] + qa[1][0]), __float_as_uint((g & 1) ? qb[0][3] + qb[1][3] : qb[0][2] + qb[1][2]));
        bar_sync(13, 128);
        float m0 = 0.f, m1 = 0.f, v0 = 0.f, v1 = 0.f;
#pragma unroll
        for (int i = 0; i < 4; i++) {
          const uint4 t = lds128(sb + SM_RED + (i * 8 + g) * 16);
          m0 += __uint_as_float(t.x); m1 += __uint_as_float(t.y); v0 += __uint_as_float(t.z); v1 += __uint_as_float(t.w);
        }
        m0 *= (1.f / 512); m1 *= (1.f / 512);
        const uint32_t mw = pack2(m0, m1), ma = dup_lo(mw), mb = dup_hi(mw);
        uint32_t t = pack2(fmaxf(fmaf(v0, 1.f / 512, -m0 * m0), 0.f), fmaxf(fmaf(v1, 1.f / 512, -m1 * m1), 0.f));
        t = pack2(blo(t) + 1e-5f, bhi(t) + 1e-5f);
        t = pack2(sqrt_ap(blo(t)), sqrt_ap(bhi(t)));
        const float r0 = rcp_ap(blo(t)), r1 = rcp_ap(bhi(t));
        const uint32_t rh = pack2(r0, r1), rl = pack2(r0 - blo(rh), r1 - bhi(rh));
        const uint32_t rha = dup_lo(rh), rhb = dup_hi(rh), rla = dup_lo(rl), rlb = dup_hi(rl);
#pragma unroll
        for (int i = 0; i < 16; i++) {
          const uint32_t da = hsub2(xa[i], ma), db = hsub2(xb[i], mb);
          na[i] = hfma2(da, rha, hmul2(da, rla)); nb[i] = hfma2(db, rhb, hmul2(db, rlb));
        }
      }
      if (phase == 1) {
#pragma unroll
        for (int i = 0; i < 4; i++) {
          uint32_t h[8];
#pragma unroll
          for (int k = 0; k < 4; k++) { h[k] = hadd2(hmul2(na[4 * i + k], cbw[4 * i + k]), sbw[4 * i + k]); h[4 + k] = hadd2(hmul2(nb[4 * i + k], cbw[4 * i + k]), sbw[4 * i + k]); }
          st_b128(p.s->H2 + (xoff >> 3) + 4 * i, (h[0] & ~1u) | par, h[1], h[2], h[3]);
          st_b128(p.s->H2 + (xoff >> 3) + 64 + 4 * i, (h[4] & ~1u) | par, h[5], h[6], h[7]);
        }
        break;
      }
      {
        uint4* dst = p.s->XM + (32 * w + 2 * c4) * 1024 + jb * 8 + g;
#pragma unroll
        for (int i = 0; i < 8; i++)
          st_b128(dst + ((i >> 1) * 8 + (i & 1)) * 1024, PLO(na[2 * i], nb[2 * i]) | 1u, PHI(na[2 * i], nb[2 * i]), PLO(na[2 * i + 1], nb[2 * i + 1]), PHI(na[2 * i + 1], nb[2 * i + 1]));
      }
      if (t2 == 0) TSTAMP(1);
      {
        uint32_t sv[4][4];
#pragma unroll
        for (int i = 0; i < 4; i++) ldsm4(sv[i], sb + SM_SV + (128 * w + 32 * i + 8 * (lane >> 3)) * 2);
        mbar_wait(barM, 0);
#pragma unroll 1
        for (int nt = 0; nt < 3; nt++) {
          const uint32_t a = sb + SM_MODS + (128 * w + lane) * 48 + 16 * nt;
          float d0[4] = {0.f, 0.f, 0.f, 0.f}, d1[4] = {0.f, 0.f, 0.f, 0.f};
#pragma unroll
          for (int i = 0; i < 4; i++) {
            uint32_t bb[4];
            ldsm4t(bb, a + 1536 * i);
            mma16816(d0, sv[i][0], sv[i][0], sv[i][1], sv[i][1], bb[0], bb[1]);
            mma16816(d1, sv[i][2], sv[i][2], sv[i][3], sv[i][3], bb[2], bb[3]);
          }
          if (g == 0) sts64f(sb + SM_REDM + w * 128 + nt * 32 + c4 * 8, d0[0] + d1[0], d0[1] + d1[1]);
        }
        bar_sync(13, 128);
        if (w == 0) {
          const uint32_t ra = sb + SM_REDM + lane * 4;
          float v = rbf(lds32f(ra) + lds32f(ra + 128) + lds32f(ra + 256) + lds32f(ra + 384));
          const int mi = (24 * b + lane) >> 9;
          if (mi == 1 || mi == 4) v += 1.f;
          const uint32_t pw = pack2(v, __shfl_down_sync(~0u, v, 1));
          const uint32_t pw2 = __shfl_down_sync(~0u, pw, 2);
          if (c4 == 0 && lane < 24) st_b128(p.s->MODX + 6 * b + g, pw, pw2, ep, 0);
        }
        if (t2 == 0) TSTAMP(2);
      }
      {
        uint4 v4[8];
        const uint4* xsrc = p.s->XM + b * 1024 + t2;
        for (int it = 0; it < SPIN_MAX; it++) {
#pragma unroll
          for (int i = 0; i < 8; i++) v4[i] = ld_b128(xsrc + 128 * i);
          if (sa.z != ep || ca.z != ep) { sa = ld_b128(p.s->MODX + b); ca = ld_b128(p.s->MODX + 128 + b); }
          bool ok = sa.z == ep && ca.z == ep;
#pragma unroll
          for (int i = 0; i < 8; i++) ok = ok && (v4[i].x & 1);
          if (ok) break;
        }
        if (t2 == 32) {
          asm volatile("cp.async.bulk.prefetch.L2.global [%0], %1;" ::"l"((const char*)p.wg + b * 14336), "r"(14336) : "memory");
          asm volatile("cp.async.bulk.prefetch.L2.global [%0], %1;" ::"l"((const char*)p.wu + b * 14336), "r"(14336) : "memory");
          asm volatile("cp.async.bulk.prefetch.L2.global [%0], %1;" ::"l"((const char*)p.wd + b * 14336), "r"(14336) : "memory");
        }
#pragma unroll
        for (int i = 0; i < 8; i++) {
          const uint32_t a = sb + SM_HCH + g * 656 + (9 + 4 * i + w) * 16 + c4 * 4;
          sts32(a, hadd2(hmul2(v4[i].x, dup_lo(ca.x)), dup_lo(sa.x)));
          sts32(a + HCH_SZ, hadd2(hmul2(v4[i].y, dup_hi(ca.x)), dup_hi(sa.x)));
          sts32(a + 2 * HCH_SZ, hadd2(hmul2(v4[i].z, dup_lo(ca.y)), dup_lo(sa.y)));
          sts32(a + 3 * HCH_SZ, hadd2(hmul2(v4[i].w, dup_hi(ca.y)), dup_hi(sa.y)));
        }
        FENCE_ASYNC();
        bar_arrive(14, 384);
        if (t2 == 0) TSTAMP(3);
      }
      bar_sync(5 + ch, 96);
      if (t2 == 0) TSTAMP(4);
      {
        const float k1024 = rbf(lds32f(kab + 2048) + lds32f(kab + 2048 + 2592));
        const uint32_t far = sb + SM_MODS + ch * 4608, qa = pq + 5184 + (8 + g - 2 * c4) * 4;
        uint32_t S[2][9];
#pragma unroll
        for (int e = 0; e < 9; e++) { S[0][e] = lds32(qa + 768 + 32 * e); S[1][e] = lds32(qa + 1152 + 32 * e); }
        const uint32_t wb = sb + SM_WIN + ch * WIN_SZ + 6144 + (lane >> 4) * 2048 + (lane & 15) * 16;
        uint32_t bb[8][4];
#pragma unroll
        for (int i = 0; i < 8; i++) ldsm4t(bb[i], wb + (i & 1) * 1024 + (i >> 1) * 256);
#pragma unroll
        for (int I0 = 0; I0 < 4; I0 += 2) {
          float acc[2][4][4];
#pragma unroll
          for (int i = 0; i < 32; i++) acc[i >> 4][(i >> 2) & 3][i & 3] = 0.f;
#pragma unroll
          for (int dd = 0; dd < 4; dd++)
#pragma unroll
            for (int ii = 0; ii < 2; ii++)
              if (I0 + ii - dd >= 0) {
                const int e = 2 * dd + 1;
#pragma unroll
                for (int n = 0; n < 2; n++) {
                  const int j = 2 * (I0 + ii - dd) + n;
                  mma16816(acc[ii][2 * n], S[0][e], S[0][e + 1], S[0][e - 1], S[0][e], bb[j][0], bb[j][1]);
                  mma16816(acc[ii][2 * n + 1], S[1][e], S[1][e + 1], S[1][e - 1], S[1][e], bb[j][2], bb[j][3]);
                }
              }
#pragma unroll
          for (int ii = 0; ii < 2; ii++)
#pragma unroll
            for (int n = 0; n < 2; n++)
#pragma unroll
              for (int hf = 0; hf < 2; hf++) {
                const int tr = 128 * hf + 16 * g + 8 * n + 2 * c4, I = I0 + ii;
                const int u0 = tr - 4 + 576, u1 = tr - 2 + 576;
                uint32_t h0 = lds32(hch + ((u0 >> 3) & 7) * 656 + (u0 >> 6) * 16 + (u0 & 7) * 2 + 64 * I), h1 = lds32(hch + ((u1 >> 3) & 7) * 656 + (u1 >> 6) * 16 + (u1 & 7) * 2 + 64 * I);
                sts64f(far + (tr + (tr >> 6) * 8) * 4 + 1152 * I, fmaf(k1024, blo(h0) + bhi(h0), acc[ii][2 * n][2 * hf] + acc[ii][2 * n + 1][2 * hf]),
                       fmaf(k1024, bhi(h0) + blo(h1), acc[ii][2 * n][2 * hf + 1] + acc[ii][2 * n + 1][2 * hf + 1]));
              }
        }
      }
      bar_arrive(11, 384);
      FENCE_ASYNC();
      asm volatile("barrier.cluster.arrive.relaxed.aligned;" ::: "memory");
      if (t2 == 0) TSTAMP(5);
      {
        const uint4* src = p.s->MODX + 384 + 32 * w + 2 * c4;
        int it = 0;
        bool ok;
        do {
          ok = true;
#pragma unroll
          for (int i = 0; i < 8; i++) {
            uint4 u = ld_b128(src + (i >> 1) * 8 + (i & 1)), v = ld_b128(src + 128 + (i >> 1) * 8 + (i & 1));
            sbw[2 * i] = u.x; sbw[2 * i + 1] = u.y; cbw[2 * i] = v.x; cbw[2 * i + 1] = v.y;
            ok = ok && u.z == ep && v.z == ep;
          }
        } while (!ok && ++it < SPIN_MAX);
      }
      {
        uint4 v[8];
        const uint4* src = p.s->YM + (jb * 128 + 32 * w + 2 * c4) * 8 + g;
        asm volatile("barrier.cluster.wait.aligned;" ::: "memory");
        { const long long t0 = clock64(); while (clock64() - t0 < YDEL) {} }
        for (int it = 0; it < SPIN_MAX; it++) {
          uint32_t t = 0;
#pragma unroll
          for (int i = 0; i < 8; i++) v[i] = ld_b128(src + ((i >> 1) * 8 + (i & 1)) * 8);
#pragma unroll
          for (int i = 0; i < 8; i++) t |= ~v[i].x;
          if (!(t & 1)) break;
        }
        bar_arrive(15, 160);
        if (t2 == 0) TSTAMP(7);
#pragma unroll
        for (int i = 0; i < 8; i++) {
          const uint32_t x0 = v[i].x;
          xa[2 * i] = hadd2(xa[2 * i], PLO(x0, v[i].y)); xb[2 * i] = hadd2(xb[2 * i], PHI(x0, v[i].y));
          xa[2 * i + 1] = hadd2(xa[2 * i + 1], PLO(v[i].z, v[i].w)); xb[2 * i + 1] = hadd2(xb[2 * i + 1], PHI(v[i].z, v[i].w));
        }
      }
    }
    bar_sync(12, 384);
    if (t2 == 0) TSTAMP(8);
    ru0 = w; rust = 4;
    if (w == 1) {
#pragma unroll 1
      for (int i = 0; i < 4; i++) {
        uint4 t;
        int it = 0;
        do t = ld_b128(p.s->MODX + 640 + 32 * i + lane); while (t.z != ep && ++it < SPIN_MAX);
        sts64(sb + SM_SV + 256 * i + lane * 8, t.x, t.y);
      }
    }
    if (w == 0) {
      int slot = 0, ph = 0;
#pragma unroll 1
      for (int d = 0; d < 16; d++) {
        mbar_wait(d < 14 ? barE + 8 * slot : d == 14 ? barQ : barF + 192, d < 14 ? ph : 0);
        if (t2 == 0) {
          const int nx = d + 3;
          const uint32_t dst = sb + SM_RING + slot * 32768, bf = barF + 8 * slot;
          if (nx < 14) {
            const bool y = nx == 8 || nx == 11;
            const int k0 = nx < 8 ? 64 * nx : y ? (nx - 8) / 3 * 256 : 128 * (nx - (nx < 11 ? 9 : 10)), z = nx < 8 ? 2 * f : y ? 48 + f : 16 + f;
            mbar_expect(bf, 32768);
            tma3d(dst, nx < 8 ? &tmG1 : y ? &tmG2 : &tmG3, bf, 0, k0, z);
            tma3d(dst + 16384, nx < 8 ? &tmU1 : y ? &tmU2 : &tmU3, bf, 0, k0, z);
          }
          if (d < 6) mbar_expect(barA + 8 * d, d < 4 ? 57344 : 32768);
          uint32_t mk = d == 9 ? 0x1 : d == 10 ? 0x6 : d == 12 ? 0x138 : d == 13 ? 0x4c0 : d == 14 ? 0x200 : d == 15 ? 0x800 : 0;
          while (mk) {
            const int pi = __ffs(mk) - 1, i = pi / 3, pt = pi - 3 * i;
            mk &= mk - 1;
            const uint32_t o = pt == 0 ? (0x040c0800u >> (8 * i)) & 255 : pt == 1 ? (0x16141004u >> (8 * i)) & 255 : (0x0a131206u >> (8 * i)) & 255;
            tma3d(sb + SM_A + o * 8192, pt == 0 ? &tmD : pt == 1 ? &tmD2 : &tmD3, barA + 8 * i, 0, pt == 0 ? 128 * f : pt == 1 ? 1024 + 64 * f : 1536 + 32 * f, 2 * ((i + 2 - 2 * rank) & 3));
          }
        }
        __syncwarp();
        if (++slot == 3) { slot = 0; ph ^= 1; }
      }
    }
    bar_sync(1, 384);
#pragma unroll
    for (int i = 0; i < 4; i++) {
      const uint32_t a = sb + SM_A + 65536 + g * 2048 + w * 256;
      sts128(a + (((4 * i + c4) ^ ((2 * g) & 7)) << 4), xa[4 * i], xa[4 * i + 1], xa[4 * i + 2], xa[4 * i + 3]);
      sts128(a + 1024 + (((4 * i + c4) ^ ((2 * g + 1) & 7)) << 4), xb[4 * i], xb[4 * i + 1], xb[4 * i + 2], xb[4 * i + 3]);
    }
    bar_arrive(3, 384);
    { const long long t0 = clock64(); while (clock64() - t0 < PDEL) {} }
  } else {
    const int half = warp >> 2, chn = 4 * b + ch;
    const uint32_t stg = stgc + half * STG_WARP;
    uint2 dsk;
    uint4 ga;
    {
      const int po = chn * 128 + 64 * half + 2 * lane;
      const float ldt = ldg_bf(p.logdt + chn);
      const uint32_t are = ldg32(p.Are + po), aim = ldg32(p.Aim + po), bre = ldg32(p.Bre + po), bim = ldg32(p.Bim + po), cre = ldg32(p.Cre + po), cim = ldg32(p.Cim + po);
      dsk = ldg64(p.dskip + 4 * b);
      ep = ld_rlx(p.s->epoch + b) + 1;
      ga = ld_b128(p.s->MODX + 256 + b);
#pragma unroll 1
      for (int k = 0; k < 4; k++) {
        uint32_t F[5];
#pragma unroll
        for (int j = 0; j < 5; j++) {
          const int L = g - 2 * c4 + 8 * j - ((0x0c0d0e0bu >> (8 * k)) & 255);
          F[j] = ((unsigned)L <= (unsigned)(2 * k + 2) ? 0x3f80u : 0u) | ((unsigned)(L - 1) <= (unsigned)(2 * k + 2) ? 0x3f800000u : 0u);
        }
        sts128(sb + SM_FT + k * 1024 + lane * 16, F[3], F[4], F[2], F[3]);
        sts128(sb + SM_FT + k * 1024 + 512 + lane * 16, F[1], F[2], F[0], F[1]);
      }
      const float dt = rbf(expf(ldt));
      float acc[6][4];
#pragma unroll
      for (int i = 0; i < 6; i++) acc[i][0] = acc[i][1] = acc[i][2] = acc[i][3] = 0.f;
      const uint32_t aa = stg + (lane & 15) * STG_PITCH + (lane >> 4) * 16;
      const uint32_t ba = stg + (16 + (lane & 7) + 8 * (lane >> 4)) * STG_PITCH + ((lane >> 3) & 1) * 16;
#pragma unroll 1
      for (int k = 0; k < 2; k++) {
        const uint32_t sel = k ? 0x3244 : 0x1044;
#define PICK(w) __uint_as_float(__byte_perm(w, 0, sel))
        cpx B, C;
        B.r = dt * PICK(bre); B.i = dt * PICK(bim); C.r = PICK(cre); C.i = PICK(cim);
        cpx W = cmul(C, B);
        W.i = -W.i;
        const float l2 = dt * PICK(are) * 1.4426950408889634f, tt = dt * PICK(aim) * 0.15915494309189535f;
        cpx r[12], v[14];
#pragma unroll
        for (int i = 0; i < 12; i++) r[i] = (i & 3) ? csq(r[i - 1]) : cexpk(l2, tt, (float)(1 << i));
        v[0].r = 1.f; v[0].i = 0.f; v[1] = r[5]; v[2] = r[6]; v[3] = cmul(r[5], r[6]);
        v[4] = W; v[5] = cmulc(W, r[2]); v[6] = cmulc(W, r[7]); v[7] = cmulc(v[5], r[7]);
        v[8] = cmulc(W, r[8]); v[9] = cmulc(v[8], r[7]); v[10] = cmulc(W, r[9]); v[11] = cmulc(v[5], r[9]);
        v[12] = cmulc(W, r[10]); v[13] = cmulc(v[12], r[9]);
        W = cmulc(W, r[11]);
        uint32_t sa = stg + lane * 4;
        sts32(sa + 56 * STG_PITCH, pack2(W.r, W.i));
#pragma unroll 1
        for (int i = 0;; i++) {
#pragma unroll
          for (int c = 0; c < 14; c++) sts32(sa + 4 * c * STG_PITCH, pack2(v[c].r, v[c].i));
          if (i == 3) break;
#pragma unroll
          for (int c = 0; c < 14; c++) v[c] = c < 4 ? cmul(v[c], r[3]) : cmulc(v[c], r[c < 8 ? 0 : (c < 10 ? 1 : 7)]);
          sa += STG_PITCH;
        }
        __syncwarp();
#pragma unroll
        for (int ks = 0; ks < 128; ks += 32) {
          uint32_t a[4], bb[3][4];
          ldsm4(a, aa + ks);
#pragma unroll
          for (int T = 0; T < 3; T++) ldsm4(bb[T], ba + T * 16 * STG_PITCH + ks);
#pragma unroll
          for (int T = 0; T < 6; T++) mma16816(acc[T], a[0], a[1], a[2], a[3], bb[T >> 1][2 * (T & 1)], bb[T >> 1][2 * (T & 1) + 1]);
        }
        __syncwarp();
      }
      const uint32_t ko = kab + half * 2592;
#pragma unroll
      for (int e = 0; e < 4; e += 2) {
        const int j = g + 4 * e;
        sts64f(ko + (8 * j + 2 * c4) * 4, acc[0][e], acc[0][e + 1]);
        sts64f(ko + (128 + 8 * j + 2 * c4) * 4, acc[1][e], acc[1][e + 1]);
        sts64f(ko + (256 + 64 * (c4 >> 1) + 2 * (c4 & 1) + 4 * j) * 4, acc[2][e], acc[2][e + 1]);
        sts32f(ko + (384 + (c4 >> 1) + 64 * (c4 & 1) + 2 * j) * 4, acc[3][e]);
        sts32f(ko + (416 + (c4 >> 1) + 64 * (c4 & 1) + 2 * j) * 4, acc[3][e + 1]);
        sts32f(ko + (512 + 32 * c4 + j) * 4, acc[4][e]);
        sts32f(ko + (528 + 32 * c4 + j) * 4, acc[4][e + 1]);
      }
      if (lane == 0) sts32f(ko + 2560, acc[5][0]);
    }
    bar_sync(1 + ch, 64);
    if (tid == 0) TSTAMP(10);
    {
      float v[11], w0[6], w1[6];
#pragma unroll
      for (int j = 0; j < 11; j++) {
        const int l = 320 * half + 32 * j + lane - 88;
        const int pos = l <= 256 ? l : min(128 + ((l + ((l >> 1) & 1)) >> 1), 384);
        v[j] = 0.f;
        if ((unsigned)l <= 514u) v[j] = lds32f(kab + pos * 4) + lds32f(kab + 2592 + pos * 4);
      }
      const int ty = lane & 3, k0 = g + 8 * half - 16;
      const uint32_t a = kab + (385 + 128 * (ty >> 1) + (ty & 1) + 2 * k0) * 4;
#pragma unroll
      for (int j = 0; j < 6; j++) {
        w0[j] = w1[j] = 0.f;
        if ((unsigned)(k0 + 16 * j) < 64u) w0[j] = lds32f(a + 128 * j) + lds32f(a + 128 * j + 2592);
        if ((unsigned)(k0 + 16 * j - 1) < 64u) w1[j] = lds32f(a + 128 * j - 8) + lds32f(a + 128 * j + 2584);
      }
      const uint32_t dst = pq + (320 * half + lane) * 8 + 64;
#pragma unroll
      for (int j = 0; j < 10; j++) {
        const uint32_t pw = pack2(v[j + 1], __shfl_sync(~0u, lane == 31 ? v[j] : v[j + 1], (lane + 31) & 31));
        sts32(dst + 256 * j, pw);
        sts32(dst + 256 * j - 60, pw);
      }
      if (half && lane >= 24) sts32(dst + 256 * 9 + 4, 0);
#pragma unroll
      for (int j = 0; j < 6; j++) sts32(pq + 5184 + ty * 384 + (k0 + 16 + 16 * j) * 4, pack2(w0[j], w1[j]));
    }
    const uint32_t win = sb + SM_WIN + ch * WIN_SZ;
    {
      uint4 F[8];
#pragma unroll
      for (int k = 0; k < 8; k++) F[k] = lds128(sb + SM_FT + k * 512 + lane * 16);
      const int u4 = 70 + 2 * (lane & 7) + (lane >> 3), u1 = u4 - 1;
      const uint32_t la4 = hch + (u4 & 7) * 656 + (u4 >> 3) * 16 + 32 * half, la1 = hch + (u1 & 7) * 656 + (u1 >> 3) * 16 + 32 * half;
      const uint32_t sa0 = win + (lane >> 4) * 3072 + (lane & 7) * 32 + ((lane >> 3) & 1) * 16 + 256 * half;
      const uint32_t sa1 = win + 6144 + (lane >> 3) * 1024 + (lane & 7) * 16 + 128 * half;
      bar_sync(14, 384);
      if (tid == 0) TSTAMP(11);
      uint32_t M[10][4];
#pragma unroll
      for (int j = 0; j < 6; j++) { ldsm4(M[j], la4 + 64 * j); if (j < 4) ldsm4(M[6 + j], la1 + 64 * j); }
      float d[6][4][4];
#pragma unroll
      for (int h = 0; h < 2; h++)
#pragma unroll
        for (int j = 0; j < 6; j++)
#pragma unroll
          for (int k = 0; k < (j < 4 ? 4 : 2); k++) {
            if (!h) d[j][k][0] = d[j][k][1] = d[j][k][2] = d[j][k][3] = 0.f;
            const int jj = k < 3 ? j : 6 + (j & 3);
            mma16816(d[j][k], F[2 * k + h].x, F[2 * k + h].y, F[2 * k + h].z, F[2 * k + h].w, M[jj][2 * h], M[jj][2 * h + 1]);
          }
#pragma unroll
      for (int j = 0; j < 6; j++) {
        stsm4t(sa0 + 512 * j, pack2(d[j][0][0], d[j][0][1]), pack2(d[j][0][2], d[j][0][3]), pack2(d[j][1][0], d[j][1][1]), pack2(d[j][1][2], d[j][1][3]));
        if (j < 4) stsm4t(sa1 + 256 * j, pack2(d[j][2][0], d[j][2][1]), pack2(d[j][2][2], d[j][2][3]), pack2(d[j][3][0], d[j][3][1]), pack2(d[j][3][2], d[j][3][3]));
      }
    }
    {
      const uint32_t far = stgc + FAR_OFF, qa = pq + 5184 + (8 + g - 2 * c4) * 4;
      uint32_t S[2][11];
#pragma unroll
      for (int e = 0; e < 11; e++) { S[0][e] = lds32(qa + 32 * e); S[1][e] = lds32(qa + 384 + 32 * e); }
      const uint32_t wa = win + (lane >> 4) * 3072 + (lane & 15) * 16;
      bar_sync(5 + ch, 96);
#pragma unroll 1
      for (int I = 2 * half; I < 12; I += 4) {
        float acc[4][4];
        uint32_t bb[6][4];
#pragma unroll
        for (int i = 0; i < 4; i++) acc[i][0] = acc[i][1] = acc[i][2] = acc[i][3] = 0.f;
#pragma unroll
        for (int dd = 0; dd < 6; dd++) {
          bb[dd][0] = bb[dd][1] = bb[dd][2] = bb[dd][3] = 0;
          if (I + 1 - dd >= 0) ldsm4t(bb[dd], wa + (I + 1 - dd) * 256);
        }
#pragma unroll
        for (int dd = 0; dd < 6; dd++) {
          if (dd < 5) {
            const int e = 2 * dd + 1;
            mma16816(acc[2], S[0][e], S[0][e + 1], S[0][e - 1], S[0][e], bb[dd][0], bb[dd][1]);
            mma16816(acc[3], S[1][e], S[1][e + 1], S[1][e - 1], S[1][e], bb[dd][2], bb[dd][3]);
          }
          if (dd > 0) {
            const int e = 2 * dd - 1;
            mma16816(acc[0], S[0][e], S[0][e + 1], S[0][e - 1], S[0][e], bb[dd][0], bb[dd][1]);
            mma16816(acc[1], S[1][e], S[1][e + 1], S[1][e - 1], S[1][e], bb[dd][2], bb[dd][3]);
          }
        }
        const uint32_t fa = far + I * 576 + lane * 8;
        sts64f(fa, acc[0][0] + acc[1][0], acc[0][1] + acc[1][1]);
        sts64f(fa + 288, acc[0][2] + acc[1][2], acc[0][3] + acc[1][3]);
        sts64f(fa + 576, acc[2][0] + acc[3][0], acc[2][1] + acc[3][1]);
        sts64f(fa + 864, acc[2][2] + acc[3][2], acc[2][3] + acc[3][3]);
      }
    }
#pragma unroll 1
    for (int cc = 2 * half; cc < 2 * half + 2; cc++) {
      float acc[16];
      const uint32_t pa = sb + SM_PQ + cc * PQ_SZ + (16 + 16 * ch + g - 2 * c4) * 8;
      const uint64_t db = mkdesc(sb + SM_HCH + cc * HCH_SZ + 144, 656, 128, 0);
      uint32_t prev = 0;
#pragma unroll
      for (int s0 = 0; s0 < 37; s0 += 13) {
        uint32_t Q[13][4];
        if (s0 == 26) wg_wait<1>();
#pragma unroll
        for (int i = 0; i < 13; i++)
          if (s0 + i < 37) {
            const uint2 t = lds64(pa + 128 * (s0 + i));
            asm volatile("mov.b32 %0, %4;\nmov.b32 %1, %5;\nmov.b32 %2, %6;\nmov.b32 %3, %4;" : "=r"(Q[i][0]), "=r"(Q[i][1]), "=r"(Q[i][2]), "=r"(Q[i][3]) : "r"(t.x), "r"(t.y), "r"(prev));
            prev = t.y;
          }
        wg_fence();
#pragma unroll
        for (int i = 0; i < 13; i++)
          if (s0 + i < 37) {
            const int bb = 3 - s0 - i;
            wgmma_rs32(acc, Q[i][0], Q[i][1], Q[i][2], Q[i][3], db + (uint64_t)(int64_t)((bb >> 2) + (bb & 3) * 82), s0 + i);
          }
        wg_commit();
      }
      wg_wait<0>();
      reg_fence(acc);
      const uint32_t na = sb + SM_STG + cc * 2 * STG_WARP + NEAR_OFF + (16 * ch + g + 136 * c4) * 4;
#pragma unroll
      for (int i = 0; i < 16; i++) sts32f(na + (8 * (i >> 2) + (i & 1)) * 272 + ((i >> 1) & 1) * 32, acc[i]);
    }
    if (tid == 0) TSTAMP(12);
    for (int it = 0; ga.z != ep && it < SPIN_MAX; it++) ga = ld_b128(p.s->MODX + 256 + b);
    bar_sync(11, 384);
#pragma unroll
    for (int jj = 0; jj < 4; jj++) {
      const int j = warp + 8 * jj;
      uint32_t o[4];
#pragma unroll
      for (int c = 0; c < 4; c++) {
        const uint32_t st = sb + SM_STG + c * 2 * STG_WARP + lane * 8;
        float2 y = lds64f(st + NEAR_OFF + j * 272);
        if (jj >= 1) { const float2 t = lds64f(st + FAR_OFF + (j - 8) * 288); y.x += t.x; y.y += t.y; }
        if (jj >= 2) { const float2 t = lds64f(sb + SM_MODS + c * 4608 + (j - 16) * 288 + lane * 8); y.x += t.x; y.y += t.y; }
        const uint32_t hw = lds32(sb + SM_HCH + c * HCH_SZ + g * 656 + (9 + j) * 16 + c4 * 4);
        const uint32_t gw = c < 2 ? ga.x : ga.y, dw = c < 2 ? dsk.x : dsk.y;
        o[c] = hmul2((c & 1) ? dup_hi(gw) : dup_lo(gw), hadd2(pack2(y.x, y.y), hmul2(hw, (c & 1) ? dup_hi(dw) : dup_lo(dw))));
      }
      st_b128(p.s->YM + ((4 * j + (lane >> 3)) * 128 + b) * 8 + (lane & 7), o[0] | 1u, o[1], o[2], o[3]);
    }
    if (tid == 0) TSTAMP(13);
    FENCE_ASYNC();
    asm volatile("barrier.cluster.arrive.relaxed.aligned;" ::: "memory");
    asm volatile("barrier.cluster.wait.aligned;" ::: "memory");
    if (warp == 0) bar_sync(15, 160);
    if (tid == 0) {
      for (int s = 0; s < 3; s++) {
        mbar_expect(barF + 8 * s, 32768);
        tma3d(sb + SM_RING + s * 32768, &tmG1, barF + 8 * s, 0, 64 * s, 2 * f);
        tma3d(sb + SM_RING + s * 32768 + 16384, &tmU1, barF + 8 * s, 0, 64 * s, 2 * f);
      }
    }
    __syncwarp();

    uint32_t act[56];
    int slot = 0, ph = 0, pslot = 0;
    const uint64_t dA = mkdesc(sb + SM_A + half * 8192, 16, 1024, 1);
    {
      float acc[128];
      const uint64_t dB = mkdesc(sb + SM_RING, 8192, 1024, 1);
      const uint4* asrc = p.s->H2 + (128 * m + 16 * warp + (lane >> 3)) * 64 + (lane & 7);
      const uint32_t adst = sb + SM_A + (16 * warp + (lane >> 3)) * 128 + (((lane & 7) ^ (lane >> 3)) << 4);
      uint4 v[4];
      {
        uint4 u[4];
#pragma unroll
        for (int i = 0; i < 4; i++) { v[i] = ld_b128(asrc + 256 * i); u[i] = ld_b128(asrc + 8 + 256 * i); }
        bar_sync(12, 384);
        int it = 0;
        while ((((v[0].x ^ ep) | (v[1].x ^ ep) | (v[2].x ^ ep) | (v[3].x ^ ep) | (u[0].x ^ ep) | (u[1].x ^ ep) | (u[2].x ^ ep) | (u[3].x ^ ep)) & 1) && ++it < SPIN_MAX) {
#pragma unroll
          for (int i = 0; i < 4; i++) { v[i] = ld_b128(asrc + 256 * i); u[i] = ld_b128(asrc + 8 + 256 * i); }
        }
#pragma unroll
        for (int i = 0; i < 4; i++) {
          sts128((adst + 512 * i) ^ ((i & 1) << 6), v[i].x, v[i].y, v[i].z, v[i].w);
          sts128((adst + 16384 + 512 * i) ^ ((i & 1) << 6), u[i].x, u[i].y, u[i].z, u[i].w);
        }
        FENCE_ASYNC();
        asrc += 16;
#pragma unroll
        for (int i = 0; i < 4; i++) v[i] = ld_b128(asrc + 256 * i);
      }
#pragma unroll 1
      for (int s = 0; s < 8; s++) {
        bar_sync(9 + half, 128);
        if (s == 0 && half == 1) bar_sync(4, 256);
        mbar_wait(barF + 8 * slot, ph);
        if (s == 0 && tid == 0) TSTAMP(14);
        const uint64_t a = dA + (uint64_t)(s * 1024), bd = dB + (uint64_t)(slot * 2048);
        wg_fence();
#pragma unroll
        for (int j = 0; j < 4; j++) wgmma_ss256(acc, a + 2 * j, bd + 128 * j, s | j);
        wg_commit();
        if (s == SKEW && half == 0) bar_arrive(4, 256);
        if (s > 0) {
          wg_wait<1>();
          if (lane == 0) mbar_arrive(barE + 8 * pslot);
        }
        if (s < 6) {
          int it = 0;
          while ((((v[0].x ^ ep) | (v[1].x ^ ep) | (v[2].x ^ ep) | (v[3].x ^ ep)) & 1) && ++it < SPIN_MAX) {
#pragma unroll
            for (int i = 0; i < 4; i++) v[i] = ld_b128(asrc + 256 * i);
          }
#pragma unroll
          for (int i = 0; i < 4; i++) sts128((adst + (s + 2) * 16384 + 512 * i) ^ ((i & 1) << 6), v[i].x, v[i].y, v[i].z, v[i].w);
          FENCE_ASYNC();
          asrc += 8;
#pragma unroll
          for (int i = 0; i < 4; i++) v[i] = ld_b128(asrc + 256 * i);
        }
        pslot = slot;
        if (++slot == 3) { slot = 0; ph ^= 1; }
      }
      wg_wait<0>();
      reg_fence(acc);
      if (lane == 0) mbar_arrive(barE + 8 * pslot);
      if (tid == 0) TSTAMP(15);
#pragma unroll
      for (int i = 0; i < 32; i++) act[i] = pack2(geglu2(acc[2 * i], acc[64 + 2 * i]), geglu2(acc[2 * i + 1], acc[65 + 2 * i]));
    }
    if (tid == 0) TSTAMP(16);
    {
      float ax[64], ay[32];
      const uint64_t dX = mkdesc(sb + SM_RING, 16384, 1024, 1), dY = mkdesc(sb + SM_RING, 16384, 512, 2);
#pragma unroll
      for (int d = 0; d < 6; d++) {
        const int sl = (d + 2) % 3;
        uint64_t da = dA;
        asm volatile("" : "+l"(da));
        mbar_wait(barF + 8 * sl, d == 0 ? 0 : d < 4 ? 1 : 0);
        wg_fence();
        if (d % 3 == 0) {
#pragma unroll
          for (int j = 0; j < 16; j++) wgmma_ss64(ay, da + (uint64_t)((d / 3 * 4 + (j >> 2)) * 1024 + 2 * (j & 3)), dY + (uint64_t)(sl * 2048 + 64 * j), d | j);
        } else {
#pragma unroll
          for (int j = 0; j < 8; j++) wgmma_ss128(ax, da + (uint64_t)((2 * (d - 1 - d / 3) + (j >> 2)) * 1024 + 2 * (j & 3)), dX + (uint64_t)(sl * 2048 + 128 * j), (d - 1) | j);
        }
        wg_commit();
        if (d > 0) {
          wg_wait<1>();
          if (lane == 0) mbar_arrive(barE + 8 * ((d + 1) % 3));
        }
        if (d == 4) {
          reg_fence(ay);
#pragma unroll
          for (int i = 0; i < 8; i++) act[48 + i] = pack2(geglu2(ay[2 * i], ay[16 + 2 * i]), geglu2(ay[2 * i + 1], ay[17 + 2 * i]));
        }
      }
      pslot = 1;
      wg_wait<0>();
      reg_fence(ax);
      if (lane == 0) { mbar_arrive(barE + 8 * pslot); mbar_arrive_cl(mapa(barP, rank ^ 1)); }
      if (tid == 0) TSTAMP(17);
#pragma unroll
      for (int i = 0; i < 16; i++) act[32 + i] = pack2(geglu2(ax[2 * i], ax[32 + 2 * i]), geglu2(ax[2 * i + 1], ax[33 + 2 * i]));
    }
    if (tid == 0) TSTAMP(18);
    {
      const uint32_t tand = c4 ? ~0u : ~1u;
      float aA[32], aB[32];
      auto issue = [&](float (&a)[32], int q, int h) {
        const uint64_t b0 = mkdesc(sb + SM_A + ((0x040c0800u >> (8 * q)) & 255) * 8192 + h * 16384, 16, 1024, 1), b1 = mkdesc(sb + SM_A + ((0x16141004u >> (8 * q)) & 255) * 8192 + h * 8192, 16, 1024, 1),
                       b2 = mkdesc(sb + SM_A + ((0x0a131206u >> (8 * q)) & 255) * 8192 + h * 4096, 16, 1024, 1);
        if (q >= 2) {
          const uint32_t blk = sb + SM_A + ((q & 1) ? 0 : 12 * 16384) + warp * 4096 + h * 2048 + lane * 16;
#pragma unroll
          for (int u = 0; u < 4; u++) {
            const uint4 t = lds128(blk + 512 * u);
            a[8 * u] = blo(t.x); a[8 * u + 1] = bhi(t.x); a[8 * u + 2] = blo(t.y); a[8 * u + 3] = bhi(t.y);
            a[8 * u + 4] = blo(t.z); a[8 * u + 5] = bhi(t.z); a[8 * u + 6] = blo(t.w); a[8 * u + 7] = bhi(t.w);
          }
          __syncwarp();
        }
        wg_fence();
#pragma unroll
        for (int kk = 0; kk < 7; kk++) {
          const uint64_t d = kk < 4 ? b0 + 256 * kk : kk < 6 ? b1 + 256 * (kk - 4) : b2;
          wgmma_rs64n(a, act[8 * kk], act[8 * kk + 1], act[8 * kk + 2], act[8 * kk + 3], d, kk | (q >> 1));
          wgmma_rs64n(a, act[8 * kk + 4], act[8 * kk + 5], act[8 * kk + 6], act[8 * kk + 7], d + 128, 1);
        }
        wg_commit();
      };
      auto epi = [&](float (&a)[32], int q, int h) {
        const uint32_t blk = sb + SM_A + ((q & 1) ? 0 : 12 * 16384) + warp * 4096;
        reg_fence(a);
        if (q < 2) {
          if (h && lane == 0) { if (q == 0) mbar_arrive_cl(mapa(barP + 8, rank ^ 1)); mbar_arrive(q ? barF + 192 : barQ); }
          mbar_wait(barP + 8 * q, 0);
          const uint32_t ra = mapa(blk + h * 2048 + lane * 16, rank ^ 1), rb = mapa(barR + 8 * q, rank ^ 1);
#pragma unroll
          for (int u = 0; u < 4; u++)
            st_async(ra + 512 * u, pack2(a[8 * u], a[8 * u + 1]), pack2(a[8 * u + 2], a[8 * u + 3]), pack2(a[8 * u + 4], a[8 * u + 5]), pack2(a[8 * u + 6], a[8 * u + 7]), rb);
        } else {
          const uint32_t sa = blk + (lane & 15) * 256 + h * 128, tor = (c4 || q == 3) ? 0u : ep & 1;
#pragma unroll
          for (int t = 0; t < 4; t++)
            stsm4(sa + (((2 * t + (lane >> 4)) ^ (lane & 7)) << 4), (pack2(a[8 * t], a[8 * t + 1]) & tand) | tor, (pack2(a[8 * t + 2], a[8 * t + 3]) & tand) | tor,
                  (pack2(a[8 * t + 4], a[8 * t + 5]) & tand) | tor, (pack2(a[8 * t + 6], a[8 * t + 7]) & tand) | tor);
          __syncwarp();
          uint4* dst = (q == 2 ? p.s->PM : p.s->XM) + ((rank * 128 + m * 8 + warp) * 4 + (f >> 1)) * 256 + (lane >> 3) * 16 + h * 8 + (lane & 7);
#pragma unroll
          for (int i = 0; i < 4; i++) {
            const uint4 t = lds128(blk + (lane >> 3) * 256 + h * 128 + (lane & 7) * 16 + 1024 * i);
            st_b128(dst + 64 * i, t.x, t.y, t.z, t.w);
          }
          if (h && q == 2) bar_arrive(1, 384);
        }
        if (h && tid == 0) TSTAMP(19 + q);
      };
#pragma unroll
      for (int q = 0; q < 4; q++) {
        if (q >= 2) mbar_wait(barR + 8 * (q - 2), 0);
        mbar_wait(barA + 8 * q, 0);
        issue(aA, q, 0);
        if (q) { wg_wait<1>(); epi(aB, q - 1, 1); }
        issue(aB, q, 1);
        wg_wait<1>();
        epi(aA, q, 0);
      }
      wg_wait<0>();
      epi(aB, 3, 1);
      bar_sync(3, 384);
      { const long long t0 = clock64(); while (clock64() - t0 < QDEL) {} }
    }
  }
#pragma unroll 1
  for (int u = ru0; u < 8; u += rust) {
    const int qa = warp < 8, row = 2 * u + (lane >> 4), cg = 16 * qa + ((lane & 15) ^ (row & 7));
    uint4 v[2][4];
    int it = 0;
    const uint32_t tg = qa ? 0 : ep;
    for (; it < SPIN_MAX; it++) {
      uint32_t t = 0;
#pragma unroll
      for (int k = 0; k < 2; k++) {
        const uint4* src = (qa ? p.s->XM : p.s->PM) + (k * 128 + jb) * 1024 + u * 32 + lane;
#pragma unroll
        for (int s = 0; s < 4; s++) v[k][s] = ld_b128(src + s * 256);
      }
#pragma unroll
      for (int s = 0; s < 8; s++) t |= v[s >> 2][s & 3].x ^ tg;
      if (!(t & 1)) break;
    }
    if (warp >= 8 && u < 4) bar_sync(2, 128);
#pragma unroll
    for (int k = 0; k < 2; k++) {
      const uint4 x1 = lds128(sb + SM_A + 65536 + row * 1024 + (qa + 2 * k) * 256 + (lane & 15) * 16);
      const uint4 gb = lds128(sb + SM_SV + cg * 16 + 512 * k);
      float a[8];
#pragma unroll
      for (int i = 0; i < 8; i++) a[i] = 0.f;
#pragma unroll
      for (int s = 0; s < 4; s++) {
        a[0] += blo(v[k][s].x); a[1] += bhi(v[k][s].x); a[2] += blo(v[k][s].y); a[3] += bhi(v[k][s].y);
        a[4] += blo(v[k][s].z); a[5] += bhi(v[k][s].z); a[6] += blo(v[k][s].w); a[7] += bhi(v[k][s].w);
      }
      *(uint4*)(p.out + (16 * b + row) * 512 + 8 * cg + 256 * k) =
          make_uint4(hadd2(x1.x, hmul2(gb.x, pack2(0.5f * a[0], 0.5f * a[1]))), hadd2(x1.y, hmul2(gb.y, pack2(0.5f * a[2], 0.5f * a[3]))),
                     hadd2(x1.z, hmul2(gb.z, pack2(0.5f * a[4], 0.5f * a[5]))), hadd2(x1.w, hmul2(gb.w, pack2(0.5f * a[6], 0.5f * a[7]))));
    }
  }
  if (tid == 0) { st_rlx(p.s->epoch + b, ep); TSTAMP(23); }
}

typedef CUresult (*EncFn)(CUtensorMap*, CUtensorMapDataType, cuuint32_t, void*, const cuuint64_t*, const cuuint64_t*, const cuuint32_t*, const cuuint32_t*,
                          CUtensorMapInterleave, CUtensorMapSwizzle, CUtensorMapL2promotion, CUtensorMapFloatOOBfill);

extern "C" void kernel_launch(void* const* d_in, const int* in_sizes, int n_in, void* d_out, int out_size) {
  static bool init = false;
  static void* scr = nullptr;
  static CUtensorMap tmG1, tmU1, tmG2, tmU2, tmG3, tmU3, tmD, tmD2, tmD3, tmM;
  static const void* key[4] = {nullptr, nullptr, nullptr, nullptr};
  if (!init || key[0] != d_in[10] || key[1] != d_in[11] || key[2] != d_in[12] || key[3] != d_in[14]) {
    void* fn = nullptr;
    cudaDriverEntryPointQueryResult qr;
    cudaGetDriverEntryPoint("cuTensorMapEncodeTiled", &fn, cudaEnableDefault, &qr);
    EncFn enc = (EncFn)fn;
    cudaGetSymbolAddress(&scr, g_s);
    cuuint32_t es[3] = {1, 1, 1};
    {
      cuuint64_t gd[3] = {64, 512, 28}, gs[2] = {3584, 128};
      cuuint32_t bx[3] = {64, 64, 2};
      enc(&tmG1, CU_TENSOR_MAP_DATA_TYPE_BFLOAT16, 3, d_in[10], gd, gs, bx, es, CU_TENSOR_MAP_INTERLEAVE_NONE, CU_TENSOR_MAP_SWIZZLE_128B, CU_TENSOR_MAP_L2_PROMOTION_L2_128B, CU_TENSOR_MAP_FLOAT_OOB_FILL_NONE);
      enc(&tmU1, CU_TENSOR_MAP_DATA_TYPE_BFLOAT16, 3, d_in[11], gd, gs, bx, es, CU_TENSOR_MAP_INTERLEAVE_NONE, CU_TENSOR_MAP_SWIZZLE_128B, CU_TENSOR_MAP_L2_PROMOTION_L2_128B, CU_TENSOR_MAP_FLOAT_OOB_FILL_NONE);
      cuuint32_t bx3[3] = {64, 128, 1};
      enc(&tmG3, CU_TENSOR_MAP_DATA_TYPE_BFLOAT16, 3, d_in[10], gd, gs, bx3, es, CU_TENSOR_MAP_INTERLEAVE_NONE, CU_TENSOR_MAP_SWIZZLE_128B, CU_TENSOR_MAP_L2_PROMOTION_L2_128B, CU_TENSOR_MAP_FLOAT_OOB_FILL_NONE);
      enc(&tmU3, CU_TENSOR_MAP_DATA_TYPE_BFLOAT16, 3, d_in[11], gd, gs, bx3, es, CU_TENSOR_MAP_INTERLEAVE_NONE, CU_TENSOR_MAP_SWIZZLE_128B, CU_TENSOR_MAP_L2_PROMOTION_L2_128B, CU_TENSOR_MAP_FLOAT_OOB_FILL_NONE);
    }
    {
      cuuint64_t gd[3] = {32, 512, 56}, gs[2] = {3584, 64};
      cuuint32_t bx[3] = {32, 256, 1};
      enc(&tmG2, CU_TENSOR_MAP_DATA_TYPE_BFLOAT16, 3, d_in[10], gd, gs, bx, es, CU_TENSOR_MAP_INTERLEAVE_NONE, CU_TENSOR_MAP_SWIZZLE_64B, CU_TENSOR_MAP_L2_PROMOTION_L2_128B, CU_TENSOR_MAP_FLOAT_OOB_FILL_NONE);
      enc(&tmU2, CU_TENSOR_MAP_DATA_TYPE_BFLOAT16, 3, d_in[11], gd, gs, bx, es, CU_TENSOR_MAP_INTERLEAVE_NONE, CU_TENSOR_MAP_SWIZZLE_64B, CU_TENSOR_MAP_L2_PROMOTION_L2_128B, CU_TENSOR_MAP_FLOAT_OOB_FILL_NONE);
    }
    {
      cuuint64_t gd[3] = {64, 1792, 8}, gs[2] = {1024, 128};
      cuuint32_t bx[3] = {64, 32, 2};
      enc(&tmD3, CU_TENSOR_MAP_DATA_TYPE_BFLOAT16, 3, d_in[12], gd, gs, bx, es, CU_TENSOR_MAP_INTERLEAVE_NONE, CU_TENSOR_MAP_SWIZZLE_128B, CU_TENSOR_MAP_L2_PROMOTION_L2_128B, CU_TENSOR_MAP_FLOAT_OOB_FILL_NONE);
      bx[1] = 64;
      enc(&tmD2, CU_TENSOR_MAP_DATA_TYPE_BFLOAT16, 3, d_in[12], gd, gs, bx, es, CU_TENSOR_MAP_INTERLEAVE_NONE, CU_TENSOR_MAP_SWIZZLE_128B, CU_TENSOR_MAP_L2_PROMOTION_L2_128B, CU_TENSOR_MAP_FLOAT_OOB_FILL_NONE);
      bx[1] = 128;
      enc(&tmD, CU_TENSOR_MAP_DATA_TYPE_BFLOAT16, 3, d_in[12], gd, gs, bx, es, CU_TENSOR_MAP_INTERLEAVE_NONE, CU_TENSOR_MAP_SWIZZLE_128B, CU_TENSOR_MAP_L2_PROMOTION_L2_128B, CU_TENSOR_MAP_FLOAT_OOB_FILL_NONE);
    }
    {
      cuuint64_t gd[2] = {3072, 512}, gs[1] = {6144};
      cuuint32_t bx[2] = {24, 256};
      enc(&tmM, CU_TENSOR_MAP_DATA_TYPE_BFLOAT16, 2, d_in[14], gd, gs, bx, es, CU_TENSOR_MAP_INTERLEAVE_NONE, CU_TENSOR_MAP_SWIZZLE_NONE, CU_TENSOR_MAP_L2_PROMOTION_NONE, CU_TENSOR_MAP_FLOAT_OOB_FILL_NONE);
    }
    cudaFuncSetAttribute(fused_kernel, cudaFuncAttributeMaxDynamicSharedMemorySize, SM_TOTAL);
    key[0] = d_in[10]; key[1] = d_in[11]; key[2] = d_in[12]; key[3] = d_in[14];
    init = true;
  }
  Params p;
  p.x = (const bf16*)d_in[0]; p.Are = (const bf16*)d_in[1]; p.Aim = (const bf16*)d_in[2]; p.Bre = (const bf16*)d_in[3]; p.Bim = (const bf16*)d_in[4];
  p.Cre = (const bf16*)d_in[5]; p.Cim = (const bf16*)d_in[6]; p.logdt = (const bf16*)d_in[7]; p.dskip = (const bf16*)d_in[8];
  p.wg = (const bf16*)d_in[10]; p.wu = (const bf16*)d_in[11]; p.wd = (const bf16*)d_in[12]; p.c = (const bf16*)d_in[13]; p.s = (Scr*)scr;
  p.out = (bf16*)d_out;
  fused_kernel<<<128, 384, SM_TOTAL, cudaStreamPerThread>>>(p, tmM, tmG1, tmU1, tmG2, tmU2, tmD, tmG3, tmU3, tmD2, tmD3);
}
```
